```python
import torch

def _softmax(x, axis=-1):
    return torch.softmax(x, dim=axis)
def _gelu(x):
    return torch.nn.functional.gelu(x, approximate="tanh")
def _silu(x):
    return torch.nn.functional.silu(x)
def _sigmoid(x):
    return torch.sigmoid(x)
def _layernorm(x, axis=-1, eps=1e-5):
    m = x.mean(dim=axis, keepdim=True)
    v = x.var(dim=axis, keepdim=True, unbiased=False)
    return (x - m) / torch.sqrt(v + eps)
def _scatter_add(tgt, idx, src, axis=0):
    return tgt.clone().index_add_(axis, idx, src)
def _segment_sum(src, seg, n):
    out = torch.zeros((n,) + src.shape[1:], dtype=src.dtype)
    return out.index_add_(0, seg, src)
def _pad(x, pw):
    flat = tuple(v for pair in reversed(pw) for v in pair)
    return torch.nn.functional.pad(x, flat)

kernel_name = 'parallel_sum__ssm_conv_h3__swiglu_ffn__prompt'

def setup_inputs():

    _w = (lambda a: (lambda t: t.to(torch.bfloat16) if t.is_floating_point() else t)(torch.as_tensor(a)))
    def _A_setup():
        B, S, D = 1, 2048, 1024
        ks = 4
        return {
            "q": _w((lambda *s: torch.randn(*s, dtype=torch.bfloat16) * 0.05)(B, S, D)),
            "k": _w((lambda *s: torch.randn(*s, dtype=torch.bfloat16) * 0.8)(B, S, D)),
            "v": _w((lambda *s: torch.randn(*s, dtype=torch.bfloat16) * 0.8)(B, S, D)),
            "shift_k": _w((lambda *s: torch.randn(*s, dtype=torch.bfloat16) * 0.8)(D, ks) * 0.5),
            "ssm_k": _w((lambda *s: torch.randn(*s, dtype=torch.bfloat16) * 0.8)(D, S) * (1.0 / S ** 0.5)),
            "ssm_D": _w((lambda *s: torch.randn(*s, dtype=torch.bfloat16) * 0.8)(D)),
        }
    _A_in = _A_setup()

    def _B_setup():
        B, S, D, F = 1, 2048, 1024, 3584
        return {
            "x": _w((lambda *s: torch.randn(*s, dtype=torch.bfloat16) * 0.05)(B, S, D)),
            "w_gate": _w((lambda *s: torch.randn(*s, dtype=torch.bfloat16) * 0.05)(D, F)),
            "w_up": _w((lambda *s: torch.randn(*s, dtype=torch.bfloat16) * 0.05)(D, F)),
            "w_down": _w((lambda *s: torch.randn(*s, dtype=torch.bfloat16) * 0.05)(F, D)),
        }
    _B_in = _B_setup()

    return {
        "A_q": _A_in["q"],
        "A_k": _A_in["k"],
        "A_v": _A_in["v"],
        "A_shift_k": _A_in["shift_k"],
        "A_ssm_k": _A_in["ssm_k"],
        "A_ssm_D": _A_in["ssm_D"],
        "B_x": _B_in["x"],
        "B_w_gate": _B_in["w_gate"],
        "B_w_up": _B_in["w_up"],
        "B_w_down": _B_in["w_down"],
    }

def reference(A_q, A_k, A_v, A_shift_k, A_ssm_k, A_ssm_D, B_x, B_w_gate, B_w_up, B_w_down):
    def _A_ref(q, k, v, shift_k, ssm_k, ssm_D):
        B, S, D = q.shape
        ks = shift_k.shape[-1]
        k_pad = _pad(k, ((0, 0), (ks - 1, 0), (0, 0)))
        k_shift = torch.zeros_like(k)
        for t in range(ks):
            k_shift = k_shift + k_pad[:, t:t + S, :] * shift_k[:, ks - 1 - t][None, None, :]
        kv = k_shift * v
        L = 2 * S
        kv_pad = _pad(kv, ((0, 0), (0, S), (0, 0)))
        kf_pad = _pad(ssm_k, ((0, 0), (0, S)))
        kv_f = (lambda x, axes=(-2,-1): torch.fft.rfft2(x.float(), dim=axes))(kv_pad[:, None, :, :], axes=(1, 2))
        kf_f = (lambda x, axes=(-2,-1): torch.fft.rfft2(x.float(), dim=axes))(kf_pad[:, None, :], axes=(1, 2))
        kf_f = (lambda x, *d: x.permute(*d))(kf_f, 1, 2, 0)
        y_f = kv_f * kf_f[None, :, :, :]
        y = (lambda x, s, axes=(-2,-1): torch.fft.irfft2(x, s=s, dim=axes).to(torch.bfloat16))(y_f, (1, L), axes=(1, 2))[:, 0, :S, :]
        y = y + kv * ssm_D[None, None, :]
        return q * y

    def _B_ref(x, w_gate, w_up, w_down):
        g = _silu(x @ w_gate)
        u = x @ w_up
        return (g * u) @ w_down

    x = A_q
    xn = _layernorm(x, axis=-1)
    return x + _A_ref(xn, A_k, A_v, A_shift_k, A_ssm_k, A_ssm_D) + _B_ref(xn, B_w_gate, B_w_up, B_w_down)
```

```cpp
#include <cuda_runtime.h>
#include <cuda_bf16.h>
#include <cuda.h>
#include <stdint.h>

typedef __nv_bfloat16 bf16;

#define IDLE_HINT_NS 2000
#define IDLE_SLEEP_NS 0
#define CONS_HINT 1000
#define END_LAG 2
#define TILE_LAG 1
#define CONV_LAG 2
#define REL_AT 0
#define AUX_SLEEP 450
#define AUX_U 2
#define HANDOFF 3
#define CONV_POS 3
#define HST_ROWS 16
#define HST_SLEEP 150
#define ZERO_SLEEP 80
#define LATE_SLOT 4

namespace {

constexpr int SEQ = 2048, DM = 1024, FF = 3584;
constexpr int NCTA = 132;
constexpr int STAGES = 4;
constexpr int A_BYTES = 128 * 64 * 2;
constexpr int STAGE_BYTES = A_BYTES + 256 * 64 * 2;
constexpr int STG_BYTES = 64 * 128 * 2;
constexpr int SMEM_BYTES = STAGES * STAGE_BYTES + 2 * STG_BYTES + 384 + 640 + 1024 + 1024;
constexpr int SEG_PITCH = 144;
constexpr int UR_OFF_O = 16 * SEG_PITCH;
constexpr int UR_PITCH = 2 * UR_OFF_O;
constexpr int UR_BYTES = UR_PITCH * 2;
constexpr int UR_SM_O = UR_OFF_O * 2 + 16;
constexpr int HB_OFF = 9344;
constexpr int HB_PAD = 8;
constexpr int HB_HALF = (128 + HB_PAD) * 16;
constexpr int CONV_TX = 2 * (UR_BYTES + 2 * HB_HALF);

constexpr int SY_LN = 32;
constexpr int SY_LQ = SY_LN + 16;
constexpr int SY_H = SY_LN + 16 * 32;
constexpr int SY_KV = SY_H + 16 * 32;
constexpr int SY_Z = SY_KV + 32;
constexpr int SY_C = SY_Z + 32;
constexpr int SY_WORDS = SY_C + 32;

__device__ __align__(1024) bf16 g_xn[SEQ * DM];
__device__ __align__(1024) bf16 g_h[SEQ * FF];
__device__ __align__(1024) bf16 g_uR[DM * UR_PITCH];
__device__ __align__(1024) bf16 g_kvD[SEQ * DM];
__device__ __align__(1024) bf16 g_yF[DM * SEQ];
__device__ __align__(1024) uint2 g_stats[SEQ];
__device__ __align__(1024) unsigned g_sync[SY_WORDS];

struct Sched { uint8_t nG1, g2tile, ka, na, kb, nb2, crank, nslots, ahalf; };
struct Params {
  const bf16* x; bf16* xn; unsigned* sync; uint2* stats; const bf16 *k, *v, *shift_k, *ssm_D;
  bf16 *out, *uR, *kvD, *yF;
  uint32_t zero, pad[7];
  uint16_t cbase[16];
  Sched sched[NCTA];
  CUtensorMap tmXn, tmWg, tmWu, tmHst, tmHld, tmWd, tmOut, tmSk, tmX, tmKd, tmY;
};

__device__ __forceinline__ uint32_t smem_u32(const void* p) { return (uint32_t)__cvta_generic_to_shared(p); }
__device__ __forceinline__ void mbar_init(uint32_t bar, uint32_t count) {
  asm volatile("mbarrier.init.shared::cta.b64 [%0], %1;" ::"r"(bar), "r"(count) : "memory");
}
__device__ __forceinline__ void mbar_expect_tx(uint32_t bar, uint32_t bytes) {
  asm volatile("mbarrier.arrive.expect_tx.shared::cta.b64 _, [%0], %1;" ::"r"(bar), "r"(bytes) : "memory");
}
__device__ __forceinline__ void mbar_arrive(uint32_t bar) {
  asm volatile("mbarrier.arrive.shared::cta.b64 _, [%0];" ::"r"(bar) : "memory");
}
__device__ __forceinline__ bool mbar_test_wait(uint32_t bar, uint32_t parity) {
  uint32_t ok;
  asm volatile("{\n.reg .pred p;\nmbarrier.test_wait.parity.shared::cta.b64 p, [%1], %2;\nselp.u32 %0, 1, 0, p;\n}\n"
               : "=r"(ok) : "r"(bar), "r"(parity) : "memory");
  return ok;
}
__device__ __forceinline__ bool mbar_try_wait(uint32_t bar, uint32_t parity) {
  uint32_t ok;
  asm volatile("{\n.reg .pred p;\nmbarrier.try_wait.parity.shared::cta.b64 p, [%1], %2;\nselp.u32 %0, 1, 0, p;\n}\n"
               : "=r"(ok) : "r"(bar), "r"(parity) : "memory");
  return ok;
}
constexpr int WAIT_LIMIT = 1 << 18;
__device__ __forceinline__ bool mbar_try_wait_hint(uint32_t bar, uint32_t parity, uint32_t ns) {
  uint32_t ok;
  asm volatile("{\n.reg .pred p;\nmbarrier.try_wait.parity.shared::cta.b64 p, [%1], %2, %3;\nselp.u32 %0, 1, 0, p;\n}\n"
               : "=r"(ok) : "r"(bar), "r"(parity), "r"(ns) : "memory");
  return ok;
}
__device__ __forceinline__ void mbar_wait(uint32_t bar, uint32_t parity) {
  if (mbar_try_wait(bar, parity)) return;
#pragma unroll 1
  for (int n = 0; n < WAIT_LIMIT; n++) {
    if (mbar_try_wait_hint(bar, parity, CONS_HINT)) break;
  }
}
__device__ __forceinline__ void mbar_wait_idle(uint32_t bar, uint32_t parity) {
  if (mbar_try_wait(bar, parity)) return;
#pragma unroll 1
  for (int n = 0; n < WAIT_LIMIT; n++) {
    if (mbar_try_wait_hint(bar, parity, IDLE_HINT_NS)) break;
    if (IDLE_SLEEP_NS) __nanosleep(IDLE_SLEEP_NS);
  }
}
__device__ __forceinline__ unsigned ld_acquire(const unsigned* p) {
  unsigned v; asm volatile("ld.acquire.gpu.global.u32 %0, [%1];" : "=r"(v) : "l"(p) : "memory"); return v;
}
__device__ __forceinline__ unsigned ld_relaxed(const unsigned* p) {
  unsigned v; asm volatile("ld.relaxed.gpu.global.u32 %0, [%1];" : "=r"(v) : "l"(p) : "memory"); return v;
}
__device__ __forceinline__ void fence_gpu() { asm volatile("fence.acq_rel.gpu;" ::: "memory"); }
__device__ __forceinline__ void red_release(unsigned* p, unsigned v) {
  asm volatile("red.release.gpu.global.add.u32 [%0], %1;" ::"l"(p), "r"(v) : "memory");
}
__device__ __forceinline__ void wait_cnt(const unsigned* p, unsigned target, unsigned sleep_ns) {
#pragma unroll 1
  for (int n = 0; n < WAIT_LIMIT && (int)(ld_acquire(p) - target) < 0; n++)
    if (sleep_ns) __nanosleep(sleep_ns);
}
__device__ __forceinline__ void tma_load_2d(uint32_t dst, const CUtensorMap* tm, int c0, int c1, uint32_t bar) {
  asm volatile("cp.async.bulk.tensor.2d.shared::cluster.global.mbarrier::complete_tx::bytes [%0], [%1, {%3, %4}], [%2];"
               ::"r"(dst), "l"(tm), "r"(bar), "r"(c0), "r"(c1) : "memory");
}
__device__ __forceinline__ uint64_t policy_evict_first() {
  uint64_t p; asm volatile("createpolicy.fractional.L2::evict_first.b64 %0, 1.0;" : "=l"(p)); return p;
}
__device__ __forceinline__ void tma_load_5d(uint32_t dst, const CUtensorMap* tm, int c0, int c2, int c4, uint32_t bar, uint64_t pol) {
  asm volatile("cp.async.bulk.tensor.5d.shared::cluster.global.mbarrier::complete_tx::bytes.L2::cache_hint [%0], [%1, {%3, %6, %4, %6, %5}], [%2], %7;"
               ::"r"(dst), "l"(tm), "r"(bar), "r"(c0), "r"(c2), "r"(c4), "r"(0), "l"(pol) : "memory");
}
__device__ __forceinline__ void tma_load_w(uint32_t dst, const CUtensorMap* tm, int row, int chunk, uint32_t bar) {
  asm volatile("cp.async.bulk.tensor.3d.shared::cluster.global.mbarrier::complete_tx::bytes [%0], [%1, {%5, %3, %4}], [%2];"
               ::"r"(dst), "l"(tm), "r"(bar), "r"(row), "r"(chunk), "r"(0) : "memory");
}
__device__ __forceinline__ void tma_load_2d_p(uint32_t dst, const CUtensorMap* tm, int c0, int c1, uint32_t bar, uint64_t pol) {
  asm volatile("cp.async.bulk.tensor.2d.shared::cluster.global.mbarrier::complete_tx::bytes.L2::cache_hint [%0], [%1, {%3, %4}], [%2], %5;"
               ::"r"(dst), "l"(tm), "r"(bar), "r"(c0), "r"(c1), "l"(pol) : "memory");
}
__device__ __forceinline__ void tma_prefetch_2d(const CUtensorMap* tm, int c0, int c1) {
  asm volatile("cp.async.bulk.prefetch.tensor.2d.L2.global [%0, {%1, %2}];" ::"l"(tm), "r"(c0), "r"(c1) : "memory");
}
__device__ __forceinline__ void tma_prefetch_5d(const CUtensorMap* tm, int c0, int c2, int c4) {
  asm volatile("cp.async.bulk.prefetch.tensor.5d.L2.global [%0, {%1, %4, %2, %4, %3}];" ::"l"(tm), "r"(c0), "r"(c2), "r"(c4), "r"(0) : "memory");
}
__device__ __forceinline__ uint2 lds64(uint32_t addr) {
  uint2 v; asm volatile("ld.shared.v2.b32 {%0, %1}, [%2];" : "=r"(v.x), "=r"(v.y) : "r"(addr) : "memory"); return v;
}
__device__ __forceinline__ void bulk_store(void* dst, uint32_t src, uint32_t bytes) {
  asm volatile("cp.async.bulk.global.shared::cta.bulk_group [%0], [%1], %2;" ::"l"(dst), "r"(src), "r"(bytes) : "memory");
}
__device__ __forceinline__ void ldmatrix_x4(uint32_t (&r)[4], uint32_t addr) {
  asm volatile("ldmatrix.sync.aligned.m8n8.x4.shared.b16 {%0, %1, %2, %3}, [%4];" : "=r"(r[0]), "=r"(r[1]), "=r"(r[2]), "=r"(r[3]) : "r"(addr) : "memory");
}
__device__ __forceinline__ void ldmatrix_x4_t(uint32_t (&r)[4], uint32_t addr) {
  asm volatile("ldmatrix.sync.aligned.m8n8.x4.trans.shared.b16 {%0, %1, %2, %3}, [%4];" : "=r"(r[0]), "=r"(r[1]), "=r"(r[2]), "=r"(r[3]) : "r"(addr) : "memory");
}
__device__ __forceinline__ void tma_load_3d(uint32_t dst, const CUtensorMap* tm, int c0, int c1, int c2, uint32_t bar, uint64_t pol) {
  asm volatile("cp.async.bulk.tensor.3d.shared::cluster.global.mbarrier::complete_tx::bytes.L2::cache_hint [%0], [%1, {%3, %4, %5}], [%2], %6;"
               ::"r"(dst), "l"(tm), "r"(bar), "r"(c0), "r"(c1), "r"(c2), "l"(pol) : "memory");
}
__device__ __forceinline__ void bulk_load(uint32_t dst, const void* src, uint32_t bytes, uint32_t bar, uint64_t pol) {
  asm volatile("cp.async.bulk.shared::cluster.global.mbarrier::complete_tx::bytes.L2::cache_hint [%0], [%1], %2, [%3], %4;"
               ::"r"(dst), "l"(src), "r"(bytes), "r"(bar), "l"(pol) : "memory");
}
__device__ __forceinline__ void tma_store_2d(const CUtensorMap* tm, uint32_t src, int c0, int c1) {
  asm volatile("cp.async.bulk.tensor.2d.global.shared::cta.bulk_group [%0, {%2, %3}], [%1];"
               ::"l"(tm), "r"(src), "r"(c0), "r"(c1) : "memory");
}
__device__ __forceinline__ void tma_reduce_add_5d(const CUtensorMap* tm, uint32_t src, int c0, int c2, int c4) {
  asm volatile("cp.reduce.async.bulk.tensor.5d.global.shared::cta.add.tile.bulk_group [%0, {%2, %5, %3, %5, %4}], [%1];"
               ::"l"(tm), "r"(src), "r"(c0), "r"(c2), "r"(c4), "r"(0) : "memory");
}
__device__ __forceinline__ void prefetch_tmap(const CUtensorMap* tm) {
  asm volatile("prefetch.tensormap [%0];" ::"l"(tm) : "memory");
}
__device__ __forceinline__ void bulk_commit() { asm volatile("cp.async.bulk.commit_group;" ::: "memory"); }
__device__ __forceinline__ void bulk_wait_read0() { asm volatile("cp.async.bulk.wait_group.read 0;" ::: "memory"); }
__device__ __forceinline__ void bulk_wait0() { asm volatile("cp.async.bulk.wait_group 0;" ::: "memory"); }
__device__ __forceinline__ void fence_proxy_async_global() { asm volatile("fence.proxy.async.global;" ::: "memory"); }
__device__ __forceinline__ void fence_proxy_async_smem() { asm volatile("fence.proxy.async.shared::cta;" ::: "memory"); }
__device__ __forceinline__ void wgmma_fence() { asm volatile("wgmma.fence.sync.aligned;" ::: "memory"); }
__device__ __forceinline__ void wgmma_commit() { asm volatile("wgmma.commit_group.sync.aligned;" ::: "memory"); }
template <int N> __device__ __forceinline__ void wgmma_wait() { asm volatile("wgmma.wait_group.sync.aligned %0;" ::"n"(N) : "memory"); }
__device__ __forceinline__ void named_bar_sync(int id, int n) { asm volatile("bar.sync %0, %1;" ::"r"(id), "r"(n) : "memory"); }
__device__ __forceinline__ void named_bar_arrive(int id, int n) { asm volatile("bar.arrive %0, %1;" ::"r"(id), "r"(n) : "memory"); }
template <int R> __device__ __forceinline__ void reg_alloc() { asm volatile("setmaxnreg.inc.sync.aligned.u32 %0;" ::"n"(R)); }
template <int R> __device__ __forceinline__ void reg_dealloc() { asm volatile("setmaxnreg.dec.sync.aligned.u32 %0;" ::"n"(R)); }
__device__ __forceinline__ void stmatrix_x4(uint32_t addr, uint32_t r0, uint32_t r1, uint32_t r2, uint32_t r3) {
  asm volatile("stmatrix.sync.aligned.m8n8.x4.shared.b16 [%0], {%1, %2, %3, %4};" ::"r"(addr), "r"(r0), "r"(r1), "r"(r2), "r"(r3) : "memory");
}
__device__ __forceinline__ uint32_t movmatrix(uint32_t a) {
  uint32_t d; asm volatile("movmatrix.sync.aligned.m8n8.trans.b16 %0, %1;" : "=r"(d) : "r"(a)); return d;
}
__device__ __forceinline__ uint32_t pack_bf16(float lo, float hi) {
  uint32_t r; asm("cvt.rn.bf16x2.f32 %0, %1, %2;" : "=r"(r) : "f"(hi), "f"(lo)); return r;
}
__device__ __forceinline__ float bf_lo(uint32_t p) { return __uint_as_float(p << 16); }
__device__ __forceinline__ float bf_hi(uint32_t p) { return __uint_as_float(p & 0xffff0000u); }
__device__ __forceinline__ float round_bf(float f) { return __bfloat162float(__float2bfloat16_rn(f)); }
__device__ __forceinline__ uint32_t bmul2(uint32_t a, uint32_t b) {
  uint32_t d; asm("mul.rn.bf16x2 %0, %1, %2;" : "=r"(d) : "r"(a), "r"(b)); return d;
}
__device__ __forceinline__ uint32_t badd2(uint32_t a, uint32_t b) {
  uint32_t d; asm("add.rn.bf16x2 %0, %1, %2;" : "=r"(d) : "r"(a), "r"(b)); return d;
}
__device__ __forceinline__ uint32_t bsub2(uint32_t a, uint32_t b) {
  uint32_t d; asm("sub.rn.bf16x2 %0, %1, %2;" : "=r"(d) : "r"(a), "r"(b)); return d;
}
__device__ __forceinline__ uint32_t prmt(uint32_t a, uint32_t b, uint32_t sel) {
  uint32_t d; asm("prmt.b32 %0, %1, %2, %3;" : "=r"(d) : "r"(a), "r"(b), "r"(sel)); return d;
}
__device__ __forceinline__ uint32_t lds32(uint32_t addr) {
  uint32_t v; asm volatile("ld.shared.b32 %0, [%1];" : "=r"(v) : "r"(addr) : "memory"); return v;
}
__device__ __forceinline__ uint4 lds128(uint32_t addr) {
  uint4 v; asm volatile("ld.shared.v4.b32 {%0, %1, %2, %3}, [%4];" : "=r"(v.x), "=r"(v.y), "=r"(v.z), "=r"(v.w) : "r"(addr) : "memory"); return v;
}
__device__ __forceinline__ uint4 ldg_nc(const void* p) {
  uint4 v; asm volatile("ld.global.nc.v4.b32 {%0, %1, %2, %3}, [%4];" : "=r"(v.x), "=r"(v.y), "=r"(v.z), "=r"(v.w) : "l"(p)); return v;
}
__device__ __forceinline__ uint4 ldg_nc_h(const void* p, uint64_t pol) {
  uint4 v; asm volatile("ld.global.nc.L2::cache_hint.v4.b32 {%0, %1, %2, %3}, [%4], %5;" : "=r"(v.x), "=r"(v.y), "=r"(v.z), "=r"(v.w) : "l"(p), "l"(pol)); return v;
}
__device__ __forceinline__ void stg128(void* p, uint4 v) {
  asm volatile("st.global.v4.b32 [%0], {%1, %2, %3, %4};" ::"l"(p), "r"(v.x), "r"(v.y), "r"(v.z), "r"(v.w) : "memory");
}
__device__ __forceinline__ int tid_fresh() { int t; asm volatile("mov.u32 %0, %%tid.x;" : "=r"(t)); return t; }
__device__ __forceinline__ uint64_t make_desc(uint32_t addr, uint32_t lbo, uint32_t sbo, uint32_t mode) {
  return (uint64_t)((addr & 0x3FFFF) >> 4) | ((uint64_t)((lbo & 0x3FFFF) >> 4) << 16) | ((uint64_t)((sbo & 0x3FFFF) >> 4) << 32) | ((uint64_t)mode << 62);
}

__device__ __forceinline__ void wgmma_ss_n256_tb(float (&d)[128], uint64_t da, uint64_t db, int scale_d) {
  asm volatile("{\n.reg .pred p;\nsetp.ne.b32 p, %130, 0;\n"
    "wgmma.mma_async.sync.aligned.m64n256k16.f32.bf16.bf16 "
    "{%0, %1, %2, %3, %4, %5, %6, %7, %8, %9, %10, %11, %12, %13, %14, %15, %16, %17, %18, %19, %20, %21, %22, %23, %24, %25, %26, %27, %28, %29, %30, %31, %32, %33, %34, %35, %36, %37, %38, %39, %40, %41, %42, %43, %44, %45, %46, %47, %48, %49, %50, %51, %52, %53, %54, %55, %56, %57, %58, %59, %60, %61, %62, %63, %64, %65, %66, %67, %68, %69, %70, %71, %72, %73, %74, %75, %76, %77, %78, %79, %80, %81, %82, %83, %84, %85, %86, %87, %88, %89, %90, %91, %92, %93, %94, %95, %96, %97, %98, %99, %100, %101, %102, %103, %104, %105, %106, %107, %108, %109, %110, %111, %112, %113, %114, %115, %116, %117, %118, %119, %120, %121, %122, %123, %124, %125, %126, %127}, "
    "%128, %129, p, 1, 1, 0, 1;\n}\n"
    : "+f"(d[0]), "+f"(d[1]), "+f"(d[2]), "+f"(d[3]), "+f"(d[4]), "+f"(d[5]), "+f"(d[6]), "+f"(d[7]), "+f"(d[8]), "+f"(d[9]), "+f"(d[10]), "+f"(d[11]), "+f"(d[12]), "+f"(d[13]), "+f"(d[14]), "+f"(d[15]), "+f"(d[16]), "+f"(d[17]), "+f"(d[18]), "+f"(d[19]), "+f"(d[20]), "+f"(d[21]), "+f"(d[22]), "+f"(d[23]), "+f"(d[24]), "+f"(d[25]), "+f"(d[26]), "+f"(d[27]), "+f"(d[28]), "+f"(d[29]), "+f"(d[30]), "+f"(d[31]), "+f"(d[32]), "+f"(d[33]), "+f"(d[34]), "+f"(d[35]), "+f"(d[36]), "+f"(d[37]), "+f"(d[38]), "+f"(d[39]), "+f"(d[40]), "+f"(d[41]), "+f"(d[42]), "+f"(d[43]), "+f"(d[44]), "+f"(d[45]), "+f"(d[46]), "+f"(d[47]), "+f"(d[48]), "+f"(d[49]), "+f"(d[50]), "+f"(d[51]), "+f"(d[52]), "+f"(d[53]), "+f"(d[54]), "+f"(d[55]), "+f"(d[56]), "+f"(d[57]), "+f"(d[58]), "+f"(d[59]), "+f"(d[60]), "+f"(d[61]), "+f"(d[62]), "+f"(d[63]), "+f"(d[64]), "+f"(d[65]), "+f"(d[66]), "+f"(d[67]), "+f"(d[68]), "+f"(d[69]), "+f"(d[70]), "+f"(d[71]), "+f"(d[72]), "+f"(d[73]), "+f"(d[74]), "+f"(d[75]), "+f"(d[76]), "+f"(d[77]), "+f"(d[78]), "+f"(d[79]), "+f"(d[80]), "+f"(d[81]), "+f"(d[82]), "+f"(d[83]), "+f"(d[84]), "+f"(d[85]), "+f"(d[86]), "+f"(d[87]), "+f"(d[88]), "+f"(d[89]), "+f"(d[90]), "+f"(d[91]), "+f"(d[92]), "+f"(d[93]), "+f"(d[94]), "+f"(d[95]), "+f"(d[96]), "+f"(d[97]), "+f"(d[98]), "+f"(d[99]), "+f"(d[100]), "+f"(d[101]), "+f"(d[102]), "+f"(d[103]), "+f"(d[104]), "+f"(d[105]), "+f"(d[106]), "+f"(d[107]), "+f"(d[108]), "+f"(d[109]), "+f"(d[110]), "+f"(d[111]), "+f"(d[112]), "+f"(d[113]), "+f"(d[114]), "+f"(d[115]), "+f"(d[116]), "+f"(d[117]), "+f"(d[118]), "+f"(d[119]), "+f"(d[120]), "+f"(d[121]), "+f"(d[122]), "+f"(d[123]), "+f"(d[124]), "+f"(d[125]), "+f"(d[126]), "+f"(d[127])
    : "l"(da), "l"(db), "r"(scale_d));
}
__device__ __forceinline__ void wgmma_rs_n32(float (&d)[16], uint32_t a0, uint32_t a1, uint32_t a2, uint32_t a3, uint64_t db, int scale_d) {
  asm volatile("{\n.reg .pred p;\nsetp.ne.b32 p, %21, 0;\n"
    "wgmma.mma_async.sync.aligned.m64n32k16.f32.bf16.bf16 "
    "{%0, %1, %2, %3, %4, %5, %6, %7, %8, %9, %10, %11, %12, %13, %14, %15}, "
    "{%16, %17, %18, %19}, %20, p, 1, 1, 0;\n}\n"
    : "+f"(d[0]), "+f"(d[1]), "+f"(d[2]), "+f"(d[3]), "+f"(d[4]), "+f"(d[5]), "+f"(d[6]), "+f"(d[7]), "+f"(d[8]), "+f"(d[9]), "+f"(d[10]), "+f"(d[11]), "+f"(d[12]), "+f"(d[13]), "+f"(d[14]), "+f"(d[15])
    : "r"(a0), "r"(a1), "r"(a2), "r"(a3), "l"(db), "r"(scale_d));
}


__device__ __forceinline__ void g1_tile(int cta, int r, int& mb, int& nb) {
  const int t = r * NCTA + cta;
  if (r < 2) { mb = r * 8 + (cta & 7); nb = cta >> 3; }
  else if (t < 2 * NCTA + 8) { const int u = t - 2 * NCTA; mb = 4 + (u & 3) + (u >> 2) * 8; nb = 16; }
  else { const int u = t - (2 * NCTA + 8); mb = u & 15; nb = 17 + (u >> 4); }
}
__device__ __forceinline__ void red_relaxed(unsigned* p, unsigned v) {
  asm volatile("red.relaxed.gpu.global.add.u32 [%0], %1;" ::"l"(p), "r"(v) : "memory");
}
struct RowStats { uint32_t m2; float rs; };
__device__ __forceinline__ RowStats ln_stats(const uint4 (&xv)[4]) {
  float s = 0.f;
#pragma unroll
  for (int i = 0; i < 4; i++) {
    s += (bf_lo(xv[i].x) + bf_hi(xv[i].x)) + (bf_lo(xv[i].y) + bf_hi(xv[i].y));
    s += (bf_lo(xv[i].z) + bf_hi(xv[i].z)) + (bf_lo(xv[i].w) + bf_hi(xv[i].w));
  }
#pragma unroll
  for (int o = 16; o > 0; o >>= 1) s += __shfl_xor_sync(0xffffffffu, s, o);
  const float m = s * (1.f / DM);
  float s0 = 0.f, s1 = 0.f;
#pragma unroll
  for (int i = 0; i < 4; i++) {
    const uint32_t e[4] = {xv[i].x, xv[i].y, xv[i].z, xv[i].w};
#pragma unroll
    for (int j = 0; j < 4; j++) { float a = bf_lo(e[j]) - m, b = bf_hi(e[j]) - m; s0 += a * a; s1 += b * b; }
  }
  s0 += s1;
#pragma unroll
  for (int o = 16; o > 0; o >>= 1) s0 += __shfl_xor_sync(0xffffffffu, s0, o);
  RowStats r;
  r.m2 = pack_bf16(m, m);
  r.rs = 1.f / round_bf(sqrtf(round_bf(round_bf(s0 * (1.f / DM)) + 1e-5f)));
  return r;
}
__device__ __forceinline__ uint32_t ln_norm2(uint32_t e, uint32_t m2, float rs) {
  const uint32_t c = bsub2(e, m2);
  return pack_bf16(bf_lo(c) * rs, bf_hi(c) * rs);
}
__device__ __forceinline__ uint4 ln_norm8(const uint4& x, const RowStats& r) {
  return make_uint4(ln_norm2(x.x, r.m2, r.rs), ln_norm2(x.y, r.m2, r.rs), ln_norm2(x.z, r.m2, r.rs), ln_norm2(x.w, r.m2, r.rs));
}

__device__ __forceinline__ uint32_t silu2(uint32_t gp) {
  float g0, g1, e0, e1, r;
  asm("max.NaN.f32 %0, %1, %2;" : "=f"(g0) : "f"(bf_lo(gp)), "f"(-41.f));
  asm("max.NaN.f32 %0, %1, %2;" : "=f"(g1) : "f"(bf_hi(gp)), "f"(-41.f));
  asm("ex2.approx.ftz.f32 %0, %1;" : "=f"(e0) : "f"(g0 * -1.4426950408889634f));
  asm("ex2.approx.ftz.f32 %0, %1;" : "=f"(e1) : "f"(g1 * -1.4426950408889634f));
  const float d0 = 1.f + e0, d1 = 1.f + e1;
  asm("rcp.approx.ftz.f32 %0, %1;" : "=f"(r) : "f"(d0 * d1));
  return pack_bf16(g0 * (d1 * r), g1 * (d0 * r));
}

template <int P> __device__ __forceinline__ void swiglu_piece(const uint32_t (&pk)[64], uint32_t sa0, uint32_t uz) {
  uint32_t r[4];
#pragma unroll
  for (int q = 0; q < 4; q++) {
    const uint32_t g = pk[4 * P + q], u = pk[32 + 4 * P + q];
    r[q] = bmul2(silu2(g), u);
  }
  const uint32_t addr = (sa0 ^ ((((2 * P) & 7) << 4) + uz)) + (P >> 2) * 8192;
  stmatrix_x4(addr, r[0], r[1], r[2], r[3]);
}

template <int K> __device__ __forceinline__ void conv_load_raw(uint32_t (&f)[17], uint32_t abase) {
#pragma unroll
  for (int n = 0; n < 17; n++) f[n] = lds32(abase + K * (4 * SEG_PITCH * 2) - 16 * (n - 1));
}
__device__ __forceinline__ void conv_expand(uint32_t (&q)[8][4], const uint32_t (&f)[17], uint32_t z) {
#pragma unroll
  for (int mm = 0; mm < 8; mm++) { q[mm][0] = f[2 * mm + 1] + z; q[mm][1] = f[2 * mm + 2] + z; q[mm][2] = f[2 * mm] ^ z; q[mm][3] = f[2 * mm + 1] ^ z; }
}
template <int K> __device__ __forceinline__ void conv_load(uint32_t (&q)[8][4], uint32_t abase) {
  q[0][2] = lds32(abase + K * (4 * SEG_PITCH * 2) + 16);
#pragma unroll
  for (int mm = 0; mm < 8; mm++) {
    q[mm][0] = lds32(abase + K * (4 * SEG_PITCH * 2) - 32 * mm);
    q[mm][1] = lds32(abase + K * (4 * SEG_PITCH * 2) - 32 * mm - 16);
  }
}
__device__ __forceinline__ void conv_fill(uint32_t (&q)[8][4], uint32_t z) {
#pragma unroll
  for (int mm = 0; mm < 8; mm++) { q[mm][3] = q[mm][0] + z; if (mm > 0) q[mm][2] = q[mm - 1][1] + z; }
}
template <int K> __device__ __forceinline__ void conv_mma(float (&d)[4][16], const uint32_t (&q)[8][4], uint64_t db) {
#pragma unroll
  for (int mm = 0; mm < 8; mm++)
#pragma unroll
    for (int b = K; b < 4; b++)
      wgmma_rs_n32(d[b], q[mm][0], q[mm][1], q[mm][2], q[mm][3], db + (32 * (b - K) - mm), (K | mm) != 0);
}


__device__ __forceinline__ int gemm_row(int s) { return ((s >> 4) & 1) | ((s >> 6) & 6) | ((s >> 2) & 24) | ((s & 15) << 5) | (s & 1536); }
__device__ __forceinline__ int time_of_row(int R) { return ((R >> 5) & 15) | ((R & 1) << 4) | ((R & 24) << 2) | ((R & 6) << 6) | (R & 1536); }
__device__ __forceinline__ void kv_unit(const Params& P, int c0, int T0, int lane, uint32_t wts, uint64_t pol) {
  const int g = lane >> 2, t = lane & 3;
  const int off = (T0 + 4 * g) * DM + c0 + 8 * t;
  uint4 kr[8], vr[5];
#pragma unroll
  for (int b = 0; b < 8; b++) kr[b] = (b >= 4 || off >= DM) ? ldg_nc_h(P.k + off + (b - 4) * DM, pol) : make_uint4(0, 0, 0, 0);
#pragma unroll
  for (int b = 0; b < 5; b++) vr[b] = (b >= 1 || off >= DM) ? ldg_nc_h(P.v + off + (b - 1) * DM, pol) : make_uint4(0, 0, 0, 0);
#pragma unroll
  for (int c = 0; c < 4; c++) {
    const uint4 q = lds128(wts + (4 * t + c) * 16);
#pragma unroll
    for (int b = 0; b < 5; b++) {
      auto comp = [&](const uint4& z) { return c == 0 ? z.x : c == 1 ? z.y : c == 2 ? z.z : z.w; };
      uint32_t a = bmul2(comp(kr[b]), q.w);
      a = badd2(a, bmul2(comp(kr[b + 1]), q.z));
      a = badd2(a, bmul2(comp(kr[b + 2]), q.y));
      a = badd2(a, bmul2(comp(kr[b + 3]), q.x));
      a = bmul2(a, comp(vr[b]));
      if (c == 0) vr[b].x = a; else if (c == 1) vr[b].y = a; else if (c == 2) vr[b].z = a; else vr[b].w = a;
    }
  }
  const uint4 dv = lds128(wts + 256 + t * 16);
  bf16* kd = P.kvD + (size_t)gemm_row(T0 + 4 * g) * DM + c0 + 8 * t;
#pragma unroll
  for (int b = 1; b < 5; b++)
    stg128(kd + (b - 1) * 32 * DM, make_uint4(bmul2(vr[b].x, dv.x), bmul2(vr[b].y, dv.y), bmul2(vr[b].z, dv.z), bmul2(vr[b].w, dv.w)));
  bf16* dst = P.uR + (size_t)(c0 + 8 * (g >> 1) + (g & 1)) * UR_PITCH + (T0 >> 7) * SEG_PITCH + (120 - (T0 & 127) - 8 * t);
  const bool halo = (T0 & 127) == 96 && t >= 2 && T0 < SEQ - 128;
#pragma unroll
  for (int c = 0; c < 4; c++) {
    uint32_t M[5];
#pragma unroll
    for (int b = 0; b < 5; b++) M[b] = movmatrix(c == 0 ? vr[b].x : c == 1 ? vr[b].y : c == 2 ? vr[b].z : vr[b].w);
    const uint4 e = make_uint4(prmt(M[3], M[2], 0x7632), prmt(M[1], M[0], 0x7632), prmt(M[3], M[2], 0x5410), prmt(M[1], M[0], 0x5410));
    const uint4 o = make_uint4(prmt(M[4], M[3], 0x7632), prmt(M[2], M[1], 0x7632), prmt(M[4], M[3], 0x5410), prmt(M[2], M[1], 0x5410));
    bf16* d = dst + 2 * c * UR_PITCH;
    stg128(d, e); stg128(d + UR_OFF_O, o);
    if (halo) { stg128(d + SEG_PITCH + 128, e); stg128(d + UR_OFF_O + SEG_PITCH + 128, o); }
    if (T0 == 0) stg128(d + 8 + 8 * t + (t >> 1) * (UR_OFF_O - 16) + 8 * t, make_uint4(0u, 0u, 0u, 0u));
  }
}

__global__ void __launch_bounds__(384, 1) fused_kernel(const __grid_constant__ Params P) {
  extern __shared__ uint8_t smem_raw[];
  const int warp = __shfl_sync(0xffffffffu, threadIdx.x >> 5, 0), lane = threadIdx.x & 31;
  const int cta = blockIdx.x;
  uint4 xa[4];
  const int lnrow = cta * 8 + warp;
  const bool do_ln = warp < 8 && cta < 128;
  if (do_ln) {
#pragma unroll
    for (int i = 0; i < 4; i++) xa[i] = ldg_nc(P.x + (size_t)time_of_row(lnrow) * DM + (lane + 32 * i) * 8);
  }
  if (warp == 9 && lane < 3) prefetch_tmap(lane == 0 ? &P.tmWg : lane == 1 ? &P.tmWu : &P.tmXn);
  const uint32_t sbase = (smem_u32(smem_raw) + 1023) & ~1023u;
  const uint32_t stg = sbase + STAGES * STAGE_BYTES;
  const uint32_t bars = stg + 2 * STG_BYTES;
  const uint32_t bar_full = bars, bar_empty = bars + 32, bar_sfull = bars + 64, bar_sempty = bars + 96;
  const uint32_t bar_oready = bars + 112, s_epoch = bars + 120, s_zero = bars + 124, bar_ln = bars + 128  , bar_go = bars + 152;
  const uint32_t bar_cdone = bars + 160  , bar_late = bars + 256, s_wts = bars + 384, s_stats = bars + 1024;
  if (threadIdx.x == 256) {
    for (int s = 0; s < STAGES; s++) { mbar_init(bar_full + 8 * s, 1); mbar_init(bar_empty + 8 * s, 2); }
    for (int w = 0; w < 4; w++) mbar_init(bar_sfull + 8 * w, 128);
    for (int w = 0; w < 2; w++) mbar_init(bar_sempty + 8 * w, 1);
    for (int w = 0; w < 3; w++) mbar_init(bar_ln + 8 * w, 8);
    for (int w = 0; w < 12; w++) mbar_init(bar_cdone + 8 * w, 8);
    mbar_init(bar_oready, 1); mbar_init(bar_go, cta < 128 ? 2 : 1); mbar_init(bar_late, 1);
    asm volatile("st.shared.u32 [%0], %1;" ::"r"(s_zero), "r"(0) : "memory");
    asm volatile("fence.mbarrier_init.release.cluster;" ::: "memory");
    fence_proxy_async_smem();
  }
  if (warp >= 10) {
    asm volatile("st.shared.v4.b32 [%0], {%1, %1, %1, %1};" ::"r"(s_stats + (threadIdx.x - 320) * 16), "r"(0) : "memory");
    fence_proxy_async_smem();
  }
  __syncthreads();
  if (do_ln) {
    const RowStats ra = ln_stats(xa);
    stg128(P.xn + (size_t)lnrow * DM + lane * 8, ln_norm8(xa[0], ra));
    stg128(P.xn + (size_t)lnrow * DM + (lane + 32) * 8, ln_norm8(xa[1], ra));
    fence_proxy_async_global();
    __syncwarp();
    if (lane == 0) { fence_gpu(); mbar_arrive(bar_ln); }
    __syncwarp();
    uint4 xb[4];
#pragma unroll
    for (int i = 0; i < 4; i++) xb[i] = ldg_nc(P.x + (size_t)(1024 + time_of_row(lnrow)) * DM + (lane + 32 * i) * 8);
    xa[2] = ln_norm8(xa[2], ra); xa[3] = ln_norm8(xa[3], ra);
    const RowStats rb = ln_stats(xb);
#pragma unroll
    for (int i = 0; i < 4; i++) xb[i] = ln_norm8(xb[i], rb);
    stg128(P.xn + (size_t)lnrow * DM + (lane + 64) * 8, xa[2]);
    stg128(P.xn + (size_t)lnrow * DM + (lane + 96) * 8, xa[3]);
#pragma unroll
    for (int i = 0; i < 4; i++) stg128(P.xn + (size_t)(1024 + lnrow) * DM + (lane + 32 * i) * 8, xb[i]);
    if (lane == 0) {
      P.stats[lnrow] = make_uint2(ra.m2, __float_as_uint(ra.rs));
      P.stats[1024 + lnrow] = make_uint2(rb.m2, __float_as_uint(rb.rs));
    }
    fence_proxy_async_global();
    __syncwarp();
    if (lane == 0) mbar_arrive(bar_ln + 8);
  } else if (warp < 8 && lane == 0) mbar_arrive(bar_ln);
  const Sched& sc = P.sched[cta];

  if (warp >= 8) {
    reg_dealloc<88>();
    const uint64_t pol = policy_evict_first();
    const int lane = tid_fresh() & 31;
    if (warp == 8) {
      unsigned epoch1 = 0;
      int mb, nb;
      g1_tile(cta, 0, mb, nb);
      auto load_w = [&](int s, int k) {
        const uint32_t sb = sbase + s * STAGE_BYTES + A_BYTES, fb = bar_full + 8 * s;
        mbar_expect_tx(fb, STAGE_BYTES);
        tma_load_w(sb, &P.tmWg, k * 64, nb * 2, fb);
        tma_load_w(sb + 16384, &P.tmWu, k * 64, nb * 2, fb);
      };
      if (lane == 0) {
        unsigned long long ticket = atomicAdd((unsigned long long*)P.sync, 1ULL);
        load_w(0, 0);
        epoch1 = (unsigned)(ticket / NCTA) + 1u;
        asm volatile("st.shared.u32 [%0], %1;" ::"r"(s_epoch), "r"(epoch1) : "memory");
        mbar_arrive(bar_go);
        mbar_wait(bar_ln, 0);
        if (cta < 128) red_relaxed(&P.sync[SY_LQ + (cta >> 4) * 32], 1u);
        load_w(1, 1);
        wait_cnt(&P.sync[SY_LQ + mb * 32], epoch1 * 16u, 0);
        fence_proxy_async_global();
#pragma unroll 1
        for (int s = 0; s < STAGES; s++) {
          if (s >= 2) load_w(s, s);
          tma_load_2d(sbase + s * STAGE_BYTES, &P.tmXn, s * 64, mb * 128, bar_full + 8 * s);
        }
      }
      epoch1 = __shfl_sync(0xffffffffu, epoch1, 0);
      int st = 0; uint32_t ph = 0;
      unsigned fl = 0;
      for (int r = 0; r <= sc.nG1; r++) {
        if (r == CONV_POS && sc.nslots) {
          if ((int)(fl - epoch1 * 8u) < 0) wait_cnt(&P.sync[SY_KV + lane], epoch1 * 8u, 0);
          __syncwarp();
          fence_proxy_async_global();
          for (int i = 0; i < sc.nslots; i++) {
            const int d = 2 * (P.cbase[i] + sc.crank);
            const uint32_t sa = sbase + st * STAGE_BYTES, fb = bar_full + 8 * st;
            mbar_wait_idle(bar_empty + 8 * st, ph); __syncwarp();
            if (lane == 0) {
              if (i == min(sc.nslots - 1, LATE_SLOT)) mbar_arrive(bar_late);
              mbar_expect_tx(fb, CONV_TX);
#pragma unroll
              for (int w = 0; w < 2; w++) {
                bulk_load(sa + w * 16384, P.uR + (size_t)(d + w) * UR_PITCH, UR_BYTES / 2, fb, pol);
                bulk_load(sa + w * 16384 + UR_SM_O, P.uR + (size_t)(d + w) * UR_PITCH + UR_OFF_O, UR_BYTES / 2, fb, pol);
                tma_load_3d(sa + w * 16384 + HB_OFF, &P.tmSk, 0, -HB_PAD, d + w, fb, pol);
                tma_load_3d(sa + w * 16384 + HB_OFF + HB_HALF, &P.tmSk, 8, -HB_PAD, d + w, fb, pol);
              }
            }
            if (++st == STAGES) { st = 0; ph ^= 1; }
          }
          if (r == sc.nG1) fl = ld_relaxed(&P.sync[SY_H + (sc.g2tile >> 2) * 32 + lane]);
        }
        if (r == sc.nG1) break;
        g1_tile(cta, r, mb, nb);
#pragma unroll 1
        for (int k = (r == 0 ? STAGES : 0); k < 16; k++) {
          mbar_wait_idle(bar_empty + 8 * st, ph); __syncwarp();
          if (lane == 0) {
            load_w(st, k);
            if (r == 0 && k == 8) {
              if ((int)(fl - epoch1 * 16u) < 0) wait_cnt(&P.sync[SY_LN + mb * 32], epoch1 * 16u, 0);
              fence_proxy_async_global();
            }
            tma_load_2d(sbase + st * STAGE_BYTES, &P.tmXn, k * 64, mb * 128, bar_full + 8 * st);
          }
          if (++st == STAGES) { st = 0; ph ^= 1; }
          if (r == 0 && k == 7) fl = ld_relaxed(&P.sync[SY_LN + mb * 32]);
          if (k == 10 && r == sc.nG1 - 1 && lane < 3) prefetch_tmap(lane == 0 ? &P.tmWd : lane == 1 ? &P.tmHld : &P.tmSk);
          if (k == 13) {
            if (r == 0) fl = ld_relaxed(&P.sync[SY_LN + (lane & 15) * 32]);
            else if (r == CONV_POS - 1 && sc.nslots) fl = ld_relaxed(&P.sync[SY_KV + lane]);
            else if (r == sc.nG1 - 1) fl = ld_relaxed(&P.sync[SY_H + (sc.g2tile >> 2) * 32 + lane]);
          }
        }
        if (r == 0) {
          if ((int)(fl - epoch1 * 16u) < 0) wait_cnt(&P.sync[SY_LN + (lane & 15) * 32], epoch1 * 16u, 0);
          __syncwarp();
          fence_proxy_async_global();
        }
      }
      mb = sc.g2tile >> 2; nb = sc.g2tile & 3;
      const unsigned* hf = &P.sync[SY_H + mb * 32 + lane];
      unsigned ready = 0;
      const int nst = sc.na + sc.nb2;
      bool polled = false;
      const int cx = sc.ahalf == 2 ? 2 : 0;
      unsigned zf = 0;
#pragma unroll 1
      for (int i = 0; i < nst; i++) {
        if (i == nst - 2) zf = ld_relaxed(&P.sync[SY_Z + lane]);
        if (i == nst - 6 && lane < 4) prefetch_tmap(lane == 0 ? &P.tmX : lane == 1 ? &P.tmKd : lane == 2 ? &P.tmY : &P.tmOut);
        const int k = i < sc.na ? sc.ka + i : sc.kb + i - sc.na;
        const uint32_t sa = sbase + st * STAGE_BYTES, sb = sa + A_BYTES, fb = bar_full + 8 * st;
        mbar_wait_idle(bar_empty + 8 * st, ph); __syncwarp();
        if (lane == 0) {
          mbar_expect_tx(fb, STAGE_BYTES);
          tma_load_w(sb, &P.tmWd, k * 64, nb * 4 + cx, fb);
          tma_load_w(sb + 16384, &P.tmWd, k * 64, nb * 4 + (2 ^ cx), fb);
        }
        if (!((ready >> (k >> 1)) & 1)) {
          ready = __ballot_sync(0xffffffffu, (int)(fl - epoch1) >= 0);
          polled = false;
#pragma unroll 1
          for (int n = 0; n < WAIT_LIMIT && !((ready >> (k >> 1)) & 1); n++) {
            fl = ld_relaxed(hf);
            ready = __ballot_sync(0xffffffffu, (int)(fl - epoch1) >= 0);
          }
          fence_proxy_async_global();
        }
        if (lane == 0) tma_load_2d_p(sa, &P.tmHld, k * 64, mb * 128, fb, pol);
        {
          const int i2 = min(i + 2, nst - 1), k2 = i2 < sc.na ? sc.ka + i2 : sc.kb + i2 - sc.na;
          if (!((ready >> (k2 >> 1)) & 1) && !polled) { fl = ld_relaxed(hf); polled = true; }
        }
        if (++st == STAGES) { st = 0; ph ^= 1; }
      }
      if (sc.ahalf) {
        mbar_wait(bar_oready, 0);
        const int col = nb * 256 + cx * 64;
        if ((lane >> 2) == (col >> 7) && (int)(zf - epoch1 * 32u) < 0) wait_cnt(&P.sync[SY_Z + lane], epoch1 * 32u, 0);
        __syncwarp();
        fence_proxy_async_global();
        for (int w = 1; w >= 0; w--) {
          const uint32_t sa = sbase + st * STAGE_BYTES, fb = bar_full + 8 * st;
          mbar_wait_idle(bar_empty + 8 * st, ph); __syncwarp();
          if (lane == 0) {
            mbar_expect_tx(fb, STAGE_BYTES + 512);
            bulk_load(s_stats + w * 512, P.stats + mb * 128 + w * 64, 512, fb, pol);
#pragma unroll
            for (int c = 0; c < 2; c++) {
              tma_load_5d(sa + c * 24576, &P.tmX, col + c * 64, (mb >> 2) * 4, (mb & 3) * 4 + w * 2, fb, pol);
              tma_load_2d_p(sa + c * 24576 + 8192, &P.tmKd, col + c * 64, mb * 128 + w * 64, fb, pol);
              tma_load_2d_p(sa + c * 24576 + 16384, &P.tmY, mb * 128 + w * 64, col + c * 64, fb, pol);
            }
          }
          if (++st == STAGES) { st = 0; ph ^= 1; }
        }
      }
    } else {
      if (warp == 9) {
        if (cta < 128) {
          if (lane == 0) {
            asm volatile("cp.async.bulk.prefetch.L2.global [%0], %1;" ::"l"(P.x + (size_t)(1024 + cta * 8) * DM), "r"(8 * DM * 2) : "memory");
            mbar_wait(bar_ln + 8, 0);
            fence_gpu();
            red_relaxed(&P.sync[SY_LN + (cta >> 4) * 32], 1u);
            red_relaxed(&P.sync[SY_LN + (8 + (cta >> 4)) * 32], 1u);
            prefetch_tmap(&P.tmHst);
            mbar_arrive(bar_go);
          }
        }
      } else {
        if (cta < 128) {
          {
            const int c0 = (cta & 15) * 64 + (warp & 1) * 32;
            const uint32_t wts = s_wts + (warp & 1) * 320;
            if (lane < 16) {
              const uint4 q = ldg_nc(P.shift_k + (size_t)(c0 + 2 * lane) * 4);
              asm volatile("st.shared.v4.b32 [%0], {%1, %2, %3, %4};" ::"r"(wts + lane * 16), "r"(prmt(q.x, q.z, 0x5410)), "r"(prmt(q.x, q.z, 0x7632)),
                           "r"(prmt(q.y, q.w, 0x5410)), "r"(prmt(q.y, q.w, 0x7632)) : "memory");
            } else if (lane < 20) {
              const uint4 q = ldg_nc(P.ssm_D + c0 + 8 * (lane - 16));
              asm volatile("st.shared.v4.b32 [%0], {%1, %2, %3, %4};" ::"r"(wts + lane * 16), "r"(q.x), "r"(q.y), "r"(q.z), "r"(q.w) : "memory");
            }
          }
          mbar_wait(bar_go, 0);
        }
        if (cta < 128) {
          const int hf = warp & 1, c0 = (cta & 15) * 64, Tb = (cta >> 4) * 256;
          const uint32_t wts = s_wts + hf * 320;
          __syncwarp();
#pragma unroll 1
          for (int i = 0; i < 8; i++) kv_unit(P, c0 + hf * 32, Tb + i * 32, lane, wts, pol);
          fence_proxy_async_global();
          fence_gpu();
          __syncwarp();
          if (lane == 0) red_relaxed(&P.sync[SY_KV + (cta & 15) * 2 + hf], 1u);
        }
        if (warp == 10 && sc.nslots && sc.crank < 64) {
          mbar_wait_idle(bar_late, 0);
          if (lane == 0) {
#pragma unroll 1
            for (int i = 0; i < 64; i++) {
              bulk_store(P.out + (size_t)sc.crank * 32 * DM + i * 512, s_stats, 1024);
              __nanosleep(ZERO_SLEEP);
            }
            bulk_commit();
            bulk_wait0();
            fence_proxy_async_global();
            red_release(&P.sync[SY_C], 1u);
          }
        }
        if (warp == 11 && sc.nslots && sc.ahalf && lane == 0) {
          mbar_wait_idle(bar_late, 0);
          const bool both = cta < 2 * (448 - 3 * NCTA);
          const int mb = sc.g2tile >> 2, col = (sc.g2tile & 3) * 256 + (sc.ahalf == 2 && !both ? 128 : 0);
#pragma unroll 1
          for (int i = 0; i < (both ? 8 : 4); i++) {
            tma_prefetch_5d(&P.tmX, col + (i >> 1) * 64, (mb >> 2) * 4, (mb & 3) * 4 + (i & 1) * 2);
            __nanosleep(AUX_SLEEP);
            tma_prefetch_2d(&P.tmKd, col + (i >> 1) * 64, mb * 128 + (i & 1) * 64);
            __nanosleep(AUX_SLEEP);
          }
        }
      }
      mbar_wait(bar_go, 0);
      const unsigned epoch1 = lds32(s_epoch);
      if (warp == 9) {
        if (lane == 0) {
          for (int r = 0; r <= sc.nG1; r++) {
            if (r == CONV_POS) {
              for (int done = 0; done < sc.nslots;) {
                mbar_wait_idle(bar_cdone + 8 * done, 0);
                int now = done + 1;
                while (now < sc.nslots && mbar_test_wait(bar_cdone + 8 * now, 0)) now++;
                fence_gpu();
                for (; done < now; done++) { red_relaxed(&P.sync[SY_Z + ((P.cbase[done] + sc.crank) >> 4)], 2u); }
              }
            }
            if (r == sc.nG1) break;
            int mb, nb;
            g1_tile(cta, r, mb, nb);
#pragma unroll 1
            for (int q = 0; q < 4; q++) {
              const int w = q & 1, bx = q >> 1;
              mbar_wait_idle(bar_sfull + 8 * q, r & 1);
#pragma unroll 1
              for (int i = 0; i < 64 / HST_ROWS; i++) {
                tma_store_2d(&P.tmHst, stg + w * STG_BYTES + bx * 8192 + i * HST_ROWS * 128, nb * 128 + bx * 64, mb * 128 + w * 64 + i * HST_ROWS);
                if (HST_SLEEP) __nanosleep(HST_SLEEP);
              }
              bulk_commit();
            }
            bulk_wait_read0();
            mbar_arrive(bar_sempty); mbar_arrive(bar_sempty + 8);
            bulk_wait0();
            fence_proxy_async_global();
            red_release(&P.sync[SY_H + mb * 32 + nb], 1u);
          }
          wait_cnt(&P.sync[SY_C], epoch1 * 64u, 200);
          fence_proxy_async_global();
          mbar_arrive(bar_oready);
        }
      }
    }
  } else {
    reg_alloc<208>();
    const int wg = warp >> 2;
    const bool leader = (tid_fresh() & 127) == 0;
    if (wg == 1) named_bar_arrive(3, 256);
    int st = 0; uint32_t ph = 0;
    float acc[128];
    uint32_t pk[64];
    bool pending = false;
    uint32_t sphase = 1;
    const uint32_t mystg = stg + wg * STG_BYTES;
    auto lane_off = [&]() { const int l = tid_fresh(); return (uint32_t)((((l >> 5) & 3) * 16 + ((l >> 3) & 1) * 8 + (l & 7)) * 128 + ((((l >> 4) & 1) ^ (l & 7)) << 4)); };
    const uint32_t sa0 = mystg + lane_off();

    for (int item = 0;; item++) {
      const bool isG2 = item == sc.nG1;
      const uint32_t uz = P.zero * item;
      if (item == CONV_POS && sc.nslots > 0) {
        swiglu_piece<1>(pk, sa0, uz); swiglu_piece<2>(pk, sa0, uz); swiglu_piece<3>(pk, sa0, uz);
        fence_proxy_async_smem();
        mbar_arrive(bar_sfull + 8 * wg);
        swiglu_piece<4>(pk, sa0, uz); swiglu_piece<5>(pk, sa0, uz); swiglu_piece<6>(pk, sa0, uz); swiglu_piece<7>(pk, sa0, uz);
        fence_proxy_async_smem();
        mbar_arrive(bar_sfull + 16 + 8 * wg);
        pending = false;
        const int lane = tid_fresh() & 31, w4 = (tid_fresh() >> 5) & 3;
        const uint32_t a_off = (uint32_t)(((lane >> 2) & 1) * (UR_SM_O / 4) + (lane >> 3) * (SEG_PITCH / 2) + 63 - w4 + (lane & 3)) * 4;
        const bool odd1 = (lane >> 3) & 1, odd2 = (lane >> 4) & 1;
        const int y_off = 8 * (lane & 7) + 64 * w4 + 256 * ((lane >> 3) & 1) + 1024 * (lane >> 4);
        for (int i = 0; i < sc.nslots; i++) {
          const int d = 2 * (P.cbase[i] + sc.crank) + wg;
          const uint32_t slot = sbase + st * STAGE_BYTES + wg * 16384;
          const uint64_t db = make_desc(slot + HB_OFF + HB_PAD * 16, HB_HALF, 128, 0);
          float cd[4][16];
          uint32_t q0[8][4], q1[8][4], q2[8][4], f3[17];
          mbar_wait(bar_full + 8 * st, ph);
          conv_load<0>(q0, slot + a_off); conv_load<1>(q1, slot + a_off); conv_load<2>(q2, slot + a_off); conv_load_raw<3>(f3, slot + a_off);
          const uint32_t zr = lds32(s_zero);
          conv_fill(q0, zr); conv_fill(q1, zr); conv_fill(q2, zr);
          named_bar_sync(3 + wg, 256);
          wgmma_fence();
          conv_mma<0>(cd, q0, db);
          wgmma_commit();
          wgmma_fence();
          conv_mma<1>(cd, q1, db); conv_mma<2>(cd, q2, db);
          wgmma_commit();
          named_bar_arrive(4 - wg, 256);
          wgmma_wait<1>();
          conv_expand(q0, f3, P.zero);
          wgmma_fence();
          conv_mma<3>(cd, q0, db);
          wgmma_commit();
          wgmma_wait<0>();
          if (leader) mbar_arrive(bar_empty + 8 * st);
          if (++st == STAGES) { st = 0; ph ^= 1; }
          float p[16][2];
#pragma unroll
          for (int j = 0; j < 16; j++)
#pragma unroll
            for (int e = 0; e < 2; e++) {
              const float m0 = j > 0 ? cd[(j - 1) >> 2][4 * ((j - 1) & 3) + e] : 0.f;
              p[j][e] = __shfl_xor_sync(0xffffffffu, odd1 ? m0 : cd[j >> 2][4 * (j & 3) + 2 + e], 8);
            }
          const bool k1 = ((__shfl_xor_sync(0xffffffffu, lane + zr, 8) >> 3) & 1) == 0;
#pragma unroll
          for (int j = 0; j < 16; j++)
#pragma unroll
            for (int e = 0; e < 2; e++) {
              const float m1 = j > 0 ? cd[(j - 1) >> 2][4 * ((j - 1) & 3) + 2 + e] : 0.f;
              p[j][e] += k1 ? m1 : cd[j >> 2][4 * (j & 3) + e];
            }
          float r[8][2];
#pragma unroll
          for (int q = 0; q < 8; q++)
#pragma unroll
            for (int e = 0; e < 2; e++) r[q][e] = __shfl_xor_sync(0xffffffffu, odd2 ? (q >= 2 ? p[q - 2][e] : 0.f) : p[8 + q][e], 16);
          const bool k2 = ((__shfl_xor_sync(0xffffffffu, lane + zr, 16) >> 4) & 1) == 0;
          uint32_t yo[8];
#pragma unroll
          for (int q = 0; q < 8; q++) yo[q] = pack_bf16(r[q][0] + (k2 ? p[6 + q][0] : p[q][0]), r[q][1] + (k2 ? p[6 + q][1] : p[q][1]));
          stg128(P.yF + (size_t)d * SEQ + y_off, make_uint4(yo[0], yo[1], yo[2], yo[3]));
          stg128(P.yF + (size_t)d * SEQ + 512 + y_off, make_uint4(yo[4], yo[5], yo[6], yo[7]));
          fence_proxy_async_global();
          __syncwarp();
          if (lane == 0) mbar_arrive(bar_cdone + 8 * i);
        }
#pragma unroll
        for (int i = 0; i < 128; i++) acc[i] = 0.f;
#pragma unroll
        for (int i = 0; i < 64; i++) pk[i] = 0u;
      }
      const int nsteps = isG2 ? (sc.na + sc.nb2) : 16;
      int prev = st;
      auto mma_issue = [&](int k, bool ord, bool rel) {
        mbar_wait(bar_full + 8 * st, ph);
        const uint32_t sa = sbase + st * STAGE_BYTES + wg * 8192, sb = sbase + st * STAGE_BYTES + A_BYTES;
        const uint64_t da = make_desc(sa, 16, 1024, 1), db = make_desc(sb, 8192, 1024, 1);
        if (ord) named_bar_sync(3 + wg, 256);
        wgmma_fence();
#pragma unroll
        for (int kk = 0; kk < 4; kk++) {
          if (ord && kk == HANDOFF) named_bar_arrive(4 - wg, 256);
          wgmma_ss_n256_tb(acc, da + kk * 2, db + kk * 128, (k | kk) != 0);
          if (kk == REL_AT) {
            wgmma_commit();
            wgmma_wait<1>();
            if (rel && leader) mbar_arrive(bar_empty + 8 * prev);
          }
        }
        if (REL_AT < 3) wgmma_commit();
        prev = st;
        if (++st == STAGES) { st = 0; ph ^= 1; }
      };
      mma_issue(0, true, false);
      if (pending) swiglu_piece<1>(pk, sa0, uz);
      mma_issue(1, true, true);
      if (pending) swiglu_piece<2>(pk, sa0, uz);
      mma_issue(2, true, true);
      if (pending) { swiglu_piece<3>(pk, sa0, uz); fence_proxy_async_smem(); mbar_arrive(bar_sfull + 8 * wg); }
      mma_issue(3, true, true);
      if (pending) swiglu_piece<4>(pk, sa0, uz);
      mma_issue(4, true, true);
      if (pending) swiglu_piece<5>(pk, sa0, uz);
      mma_issue(5, true, true);
      if (pending) swiglu_piece<6>(pk, sa0, uz);
      mma_issue(6, true, true);
      if (pending) { swiglu_piece<7>(pk, sa0, uz); fence_proxy_async_smem(); mbar_arrive(bar_sfull + 16 + 8 * wg); }
      const int lag = isG2 ? END_LAG : (item == CONV_POS - 1 && sc.nslots > 0) ? CONV_LAG : TILE_LAG;
      const bool stagger = lag > 0;
      for (int k = 7; k < nsteps; k++) {
        const bool pause = stagger && wg == 1 && k == nsteps - lag;
        if (pause) {
          wgmma_wait<0>();
          if (leader) mbar_arrive(bar_empty + 8 * prev);
          named_bar_sync(6, 256);
        }
        mma_issue(k, false, !pause);
        if (stagger && wg == 0 && k == nsteps - 1) named_bar_arrive(6, 256);
      }
      wgmma_wait<0>();
      if (leader) mbar_arrive(bar_empty + 8 * prev);
      if (isG2) break;
#pragma unroll
      for (int i = 0; i < 64; i++) pk[i] = pack_bf16(acc[2 * i], acc[2 * i + 1]);
      mbar_wait(bar_sempty + 8 * wg, sphase); sphase ^= 1;
      swiglu_piece<0>(pk, sa0, uz);
      pending = true;
    }
    {
      const int mb = sc.g2tile >> 2, col = (sc.g2tile & 3) * 256, cx = sc.ahalf == 2 ? 2 : 0;
      const int c2 = (mb >> 2) * 4, c4 = (mb & 3) * 4 + wg * 2;
      const int lane = tid_fresh() & 31, w4 = (tid_fresh() >> 5) & 3;
      const uint32_t loff = lane_off();
      auto plain_box = [&](int bx, uint32_t buf) {
#pragma unroll
        for (int jj = 0; jj < 4; jj++) {
          const int i = bx * 32 + jj * 8;
          stmatrix_x4(buf + (loff ^ ((2 * jj) << 4)), pack_bf16(acc[i], acc[i + 1]), pack_bf16(acc[i + 2], acc[i + 3]),
                      pack_bf16(acc[i + 4], acc[i + 5]), pack_bf16(acc[i + 6], acc[i + 7]));
        }
      };
      const uint32_t b2 = sbase + ((st + 2) & 3) * STAGE_BYTES + wg * 8192, b3 = sbase + ((st + 3) & 3) * STAGE_BYTES + wg * 8192;
      plain_box(2, b2); plain_box(3, b3);
      mbar_wait(bar_sempty + 8 * wg, sphase);
      plain_box(0, mystg); plain_box(1, mystg + 8192);
      {
        fence_proxy_async_smem();
        named_bar_sync(1 + wg, 128);
        if (leader) {
          mbar_wait(bar_oready, 0);
          tma_reduce_add_5d(&P.tmOut, b2, col + (2 ^ cx) * 64, c2, c4);
          tma_reduce_add_5d(&P.tmOut, b3, col + (3 ^ cx) * 64, c2, c4);
        }
      }
      if (sc.ahalf) {
        if (wg == 0) { if (++st == STAGES) { st = 0; ph ^= 1; } }
        const uint32_t yoff = ((lane >> 4) * 8 + (lane & 7)) * 128 + (((2 * w4 + ((lane >> 3) & 1)) ^ (lane & 7)) << 4);
        mbar_wait(bar_full + 8 * st, ph);
        const uint2 s0 = lds64(s_stats + (wg * 64 + w4 * 16 + (lane >> 2)) * 8), s1 = lds64(s_stats + (wg * 64 + w4 * 16 + (lane >> 2)) * 8 + 64);
#pragma unroll 1
        for (int i = 0; i < 8; i += AUX_U) {
          uint32_t x[AUX_U][4], kd[AUX_U][4], y[AUX_U][4], o[AUX_U][4];
          const uint32_t box = sbase + st * STAGE_BYTES + (i >> 2) * 24576, obox = mystg + (i >> 2) * 8192;
#pragma unroll
          for (int u = 0; u < AUX_U; u++) {
            const uint32_t lo = loff ^ (((i + u) & 3) << 5);
            ldmatrix_x4(x[u], box + lo);
            ldmatrix_x4(kd[u], box + 8192 + lo);
            ldmatrix_x4_t(y[u], box + 16384 + ((i + u) & 3) * 2048 + yoff);
            ldmatrix_x4(o[u], obox + lo);
          }
#pragma unroll
          for (int u = 0; u < AUX_U; u++) {
#pragma unroll
            for (int q = 0; q < 4; q++) {
              const uint2& s = (q & 1) ? s1 : s0;
              o[u][q] = badd2(badd2(x[u][q], bmul2(ln_norm2(x[u][q], s.x, __uint_as_float(s.y)), badd2(y[u][q], kd[u][q]))), o[u][q]);
            }
            stmatrix_x4(obox + (loff ^ (((i + u) & 3) << 5)), o[u][0], o[u][1], o[u][2], o[u][3]);
          }
        }
      }
      fence_proxy_async_smem();
      named_bar_sync(1 + wg, 128);
      if (leader) {
        tma_reduce_add_5d(&P.tmOut, mystg, col + cx * 64, c2, c4);
        tma_reduce_add_5d(&P.tmOut, mystg + 8192, col + (1 ^ cx) * 64, c2, c4);
        bulk_commit();
      }
      if (leader) bulk_wait_read0();
    }
  }
}

typedef CUresult (*PFN_encodeTiled)(CUtensorMap*, CUtensorMapDataType, cuuint32_t, void*, const cuuint64_t*, const cuuint64_t*,
                                    const cuuint32_t*, const cuuint32_t*, CUtensorMapInterleave, CUtensorMapSwizzle,
                                    CUtensorMapL2promotion, CUtensorMapFloatOOBfill);

#define PROMO CU_TENSOR_MAP_L2_PROMOTION_L2_128B
void make_tmap_2d(PFN_encodeTiled enc, CUtensorMap* m, const void* ptr, uint64_t rows, uint64_t cols, uint32_t brows, uint32_t bcols) {
  cuuint64_t dims[2] = {cols, rows};
  cuuint64_t strides[1] = {cols * 2};
  cuuint32_t box[2] = {bcols, brows};
  cuuint32_t es[2] = {1, 1};
  enc(m, CU_TENSOR_MAP_DATA_TYPE_BFLOAT16, 2, (void*)ptr, dims, strides, box, es, CU_TENSOR_MAP_INTERLEAVE_NONE,
      CU_TENSOR_MAP_SWIZZLE_128B, PROMO, CU_TENSOR_MAP_FLOAT_OOB_FILL_NONE);
}

void make_tmap_w(PFN_encodeTiled enc, CUtensorMap* m, const void* ptr, uint64_t rows, uint64_t cols) {
  cuuint64_t dims[3] = {64, rows, cols / 64};
  cuuint64_t strides[2] = {cols * 2, 128};
  cuuint32_t box[3] = {64, 64, 2};
  cuuint32_t es[3] = {1, 1, 1};
  enc(m, CU_TENSOR_MAP_DATA_TYPE_BFLOAT16, 3, (void*)ptr, dims, strides, box, es, CU_TENSOR_MAP_INTERLEAVE_NONE,
      CU_TENSOR_MAP_SWIZZLE_128B, PROMO, CU_TENSOR_MAP_FLOAT_OOB_FILL_NONE);
}

void make_tmap_5d(PFN_encodeTiled enc, CUtensorMap* m, const void* ptr) {
  cuuint64_t dims[5] = {DM, 2, 16, 4, 16};
  cuuint64_t strides[4] = {16 * DM * 2, 128 * DM * 2, 32 * DM * 2, DM * 2};
  cuuint32_t box[5] = {64, 2, 4, 4, 2};
  cuuint32_t es[5] = {1, 1, 1, 1, 1};
  enc(m, CU_TENSOR_MAP_DATA_TYPE_BFLOAT16, 5, (void*)ptr, dims, strides, box, es, CU_TENSOR_MAP_INTERLEAVE_NONE,
      CU_TENSOR_MAP_SWIZZLE_128B, CU_TENSOR_MAP_L2_PROMOTION_L2_128B, CU_TENSOR_MAP_FLOAT_OOB_FILL_NONE);
}

#define COST_G1 16950
#define COST_CP 3270
#define COST_ST 1050
#define COST_FLUSH 2100
#define COST_X4 2000
#define COST_AUX 800

void build_schedule(Sched* s, uint16_t* cbase) {
  const int n4 = 448 - 3 * NCTA;
  int mem[64][3], np[64];
  int tile = 0, c = 2 * n4;
  for (int i = 0; i < n4; i++, tile++) { np[tile] = 2; mem[tile][0] = i; mem[tile][1] = n4 + i; }
  for (; tile < 60; tile++, c += 2) { np[tile] = 2; mem[tile][0] = c; mem[tile][1] = c + 1; }
  for (; tile < 64; tile++, c += 3) { np[tile] = 3; mem[tile][0] = c; mem[tile][1] = c + 1; mem[tile][2] = c + 2; }
  double base[NCTA], work[64];
  for (int t = 0; t < 64; t++) {
    work[t] = 56.0 * COST_ST;
    for (int i = 0; i < np[t]; i++) {
      const int q = mem[t][i];
      s[q].nG1 = q < n4 ? 4 : 3; s[q].nslots = 0; s[q].crank = 0; s[q].g2tile = t; s[q].ahalf = i < 2 ? i + 1 : 0;
      base[q] = s[q].nG1 * (double)COST_G1 + (q < n4 ? COST_X4 : COST_FLUSH) + (i < 2 ? COST_AUX : 0);
      work[t] += base[q];
    }
  }
  for (int p = 0; p < 512; p++) {
    int bt = 0;
    for (int t = 1; t < 64; t++) if ((work[t] + COST_CP) / np[t] < (work[bt] + COST_CP) / np[bt]) bt = t;
    int q = -1;
    for (int i = 0; i < np[bt]; i++) { const int m = mem[bt][i]; if (m >= n4 && (q < 0 || s[m].nslots < s[q].nslots)) q = m; }
    s[q].nslots++; base[q] += COST_CP; work[bt] += COST_CP;
  }
  for (int t = 0; t < 64; t++) {
    int n[3] = {0, 0, 0};
    for (int k = 0; k < 56; k++) {
      int bi = 0;
      for (int i = 1; i < np[t]; i++) if (base[mem[t][i]] + n[i] * (double)COST_ST < base[mem[t][bi]] + n[bi] * (double)COST_ST) bi = i;
      n[bi]++;
    }
    int ea = 0, la = 40, acc = 0;
    for (int i = 0; i < np[t]; i++) {
      acc += n[i];
      const int lend = 40 + (16 * acc + 28) / 56, l = lend - la, e = n[i] - l;
      Sched& q = s[mem[t][i]];
      q.ka = ea; q.na = e; q.kb = la; q.nb2 = l;
      ea += e; la = lend;
    }
  }
  int rank = 0;
  for (int n = 15; n >= 1; n--)
    for (int i = 0; i < NCTA; i++) if (s[i].nslots == n) s[i].crank = rank++;
  int first = 0;
  for (int sl = 0; sl < 16; sl++) {
    cbase[sl] = first;
    for (int i = 0; i < NCTA; i++) if (s[i].nslots > sl) first++;
  }
}

}

extern "C" void kernel_launch(void* const* d_in, const int* in_sizes, int n_in, void* d_out, int out_size) {
  static PFN_encodeTiled enc = nullptr;
  static void *p_xn = nullptr, *p_h = nullptr, *p_kd = nullptr, *p_y = nullptr, *p_ur = nullptr, *p_st = nullptr, *p_sy = nullptr;
  if (!enc) {
    void* p = nullptr; cudaDriverEntryPointQueryResult st;
    cudaGetDriverEntryPoint("cuTensorMapEncodeTiled", &p, cudaEnableDefault, &st);
    enc = (PFN_encodeTiled)p;
    cudaGetSymbolAddress(&p_xn, g_xn);
    cudaGetSymbolAddress(&p_h, g_h);
    cudaGetSymbolAddress(&p_kd, g_kvD);
    cudaGetSymbolAddress(&p_y, g_yF);
    cudaGetSymbolAddress(&p_ur, g_uR);
    cudaGetSymbolAddress(&p_st, g_stats);
    cudaGetSymbolAddress(&p_sy, g_sync);
    cudaFuncSetAttribute(fused_kernel, cudaFuncAttributeMaxDynamicSharedMemorySize, SMEM_BYTES);
  }
  Params P;
  P.x = (const bf16*)d_in[0]; P.k = (const bf16*)d_in[1]; P.v = (const bf16*)d_in[2];
  P.shift_k = (const bf16*)d_in[3]; P.ssm_D = (const bf16*)d_in[5];
  P.out = (bf16*)d_out;
  P.zero = 0;
  P.xn = (bf16*)p_xn; P.sync = (unsigned*)p_sy; P.stats = (uint2*)p_st; P.uR = (bf16*)p_ur; P.kvD = (bf16*)p_kd; P.yF = (bf16*)p_y;
  make_tmap_2d(enc, &P.tmXn, p_xn, SEQ, DM, 128, 64);
  make_tmap_w(enc, &P.tmWg, d_in[7], DM, FF);
  make_tmap_w(enc, &P.tmWu, d_in[8], DM, FF);
  make_tmap_2d(enc, &P.tmHst, p_h, SEQ, FF, HST_ROWS, 64);
  make_tmap_2d(enc, &P.tmHld, p_h, SEQ, FF, 128, 64);
  make_tmap_w(enc, &P.tmWd, d_in[9], FF, DM);
  make_tmap_5d(enc, &P.tmOut, d_out);
  make_tmap_5d(enc, &P.tmX, d_in[0]);
  make_tmap_2d(enc, &P.tmKd, p_kd, SEQ, DM, 64, 64);
  make_tmap_2d(enc, &P.tmY, p_y, DM, SEQ, 64, 64);
  {
    cuuint64_t dims[3] = {16, 128, DM};
    cuuint64_t strides[2] = {32, SEQ * 2};
    cuuint32_t box[3] = {8, 128 + HB_PAD, 1};
    cuuint32_t es[3] = {1, 1, 1};
    enc(&P.tmSk, CU_TENSOR_MAP_DATA_TYPE_BFLOAT16, 3, d_in[4], dims, strides, box, es, CU_TENSOR_MAP_INTERLEAVE_NONE,
        CU_TENSOR_MAP_SWIZZLE_NONE, CU_TENSOR_MAP_L2_PROMOTION_L2_256B, CU_TENSOR_MAP_FLOAT_OOB_FILL_NONE);
  }
  build_schedule(P.sched, P.cbase);
  fused_kernel<<<NCTA, 384, SMEM_BYTES>>>(P);
}
```
